```python
import torch

def _softmax(x, axis=-1):
    return torch.softmax(x, dim=axis)
def _gelu(x):
    return torch.nn.functional.gelu(x, approximate="tanh")
def _silu(x):
    return torch.nn.functional.silu(x)
def _sigmoid(x):
    return torch.sigmoid(x)
def _layernorm(x, axis=-1, eps=1e-5):
    m = x.mean(dim=axis, keepdim=True)
    v = x.var(dim=axis, keepdim=True, unbiased=False)
    return (x - m) / torch.sqrt(v + eps)
def _scatter_add(tgt, idx, src, axis=0):
    return tgt.clone().index_add_(axis, idx, src)
def _segment_sum(src, seg, n):
    out = torch.zeros((n,) + src.shape[1:], dtype=src.dtype)
    return out.index_add_(0, seg, src)
def _pad(x, pw):
    flat = tuple(v for pair in reversed(pw) for v in pair)
    return torch.nn.functional.pad(x, flat)

kernel_name = 'gated_mix__gqa_block_cached__mixer_channel_mlp__decode'

def setup_inputs():

    _w = (lambda a: (lambda t: t.to(torch.bfloat16) if t.is_floating_point() else t)(torch.as_tensor(a)))
    def _A_setup():
        B, Sq, D = 4, 1, 1024
        Hq, Hkv, Sk, Dh = 32, 4, 8192, 128
        assert Hq % Hkv == 0, (Hq, Hkv)
        return {
            "x": _w((lambda *s: torch.randn(*s, dtype=torch.bfloat16) * 0.05)(B, Sq, D)),
            "k_cache": _w((lambda *s: torch.randn(*s, dtype=torch.bfloat16) * 6.4)(B, Hkv, Sk, Dh)),
            "v_cache": _w((lambda *s: torch.randn(*s, dtype=torch.bfloat16) * 0.4)(B, Hkv, Sk, Dh)),
            "wq": _w((lambda *s: torch.randn(*s, dtype=torch.bfloat16) * 6.4)(D, Hq * Dh) * (D ** -0.5)),
            "wo": _w((lambda *s: torch.randn(*s, dtype=torch.bfloat16) * 0.4)(Hq * Dh, D) * ((Hq * Dh) ** -0.5)),
        }
    _A_in = _A_setup()

    def _B_setup():
        B, S, D, F = 4, 1, 1024, 3584
        return {
            "x": _w((lambda *s: torch.randn(*s, dtype=torch.bfloat16) * 0.05)(B, S, D)),
            "w1": _w((lambda *s: torch.randn(*s, dtype=torch.bfloat16) * 0.8)(D, F) * (D ** -0.5)),
            "b1": _w((lambda *s: torch.randn(*s, dtype=torch.bfloat16) * 0.4)(F)),
            "w2": _w((lambda *s: torch.randn(*s, dtype=torch.bfloat16) * 0.05)(F, D) * (F ** -0.5)),
            "b2": _w((lambda *s: torch.randn(*s, dtype=torch.bfloat16) * 0.05)(D)),
        }
    _B_in = _B_setup()

    return {
        "A_x": _A_in["x"],
        "A_k_cache": _A_in["k_cache"],
        "A_v_cache": _A_in["v_cache"],
        "A_wq": _A_in["wq"],
        "A_wo": _A_in["wo"],
        "B_x": _B_in["x"],
        "B_w1": _B_in["w1"],
        "B_b1": _B_in["b1"],
        "B_w2": _B_in["w2"],
        "B_b2": _B_in["b2"],
        "gate_w": _w((lambda *s: torch.randn(*s, dtype=torch.bfloat16) * 0.05)(1024) * 16.0),
    }

def reference(A_x, A_k_cache, A_v_cache, A_wq, A_wo, B_x, B_w1, B_b1, B_w2, B_b2, gate_w):
    def _A_ref(x, k_cache, v_cache, wq, wo):
        B, Sq, D = x.shape
        Hq, Dh = 32, 128
        Hkv = k_cache.shape[1]
        rep = Hq // Hkv
        q = (lambda x, *d: x.permute(*d))((x @ wq).reshape(B, Sq, Hq, Dh), 0, 2, 1, 3)
        k = (lambda x, n, axis: torch.repeat_interleave(x, n, dim=axis))(k_cache, rep, axis=1)
        v = (lambda x, n, axis: torch.repeat_interleave(x, n, dim=axis))(v_cache, rep, axis=1)
        scores = torch.einsum("bhqd,bhkd->bhqk", q, k) * (Dh ** -0.5)
        p = _softmax(scores, axis=-1)
        o = torch.einsum("bhqk,bhkd->bhqd", p, v)
        return (lambda x, *d: x.permute(*d))(o, 0, 2, 1, 3).reshape(B, Sq, Hq * Dh) @ wo

    def _B_ref(x, w1, b1, w2, b2):
        y = _layernorm(x, axis=-1)
        h = _gelu(torch.einsum("bsd,df->bsf", y, w1) + b1)
        return torch.einsum("bsf,fd->bsd", h, w2) + b2

    x = A_x
    g = _sigmoid((x * gate_w).sum(-1, keepdims=True))
    a = _A_ref(x, A_k_cache, A_v_cache, A_wq, A_wo)
    b = _B_ref(x, B_w1, B_b1, B_w2, B_b2)
    return g * a + (1 - g) * b
```

```cpp
#include <cuda_runtime.h>
#include <cuda_bf16.h>
#include <cuda.h>
#include <stdint.h>

#define KTIMING 0

namespace {

constexpr int NCTA        = 128;
constexpr int NSTAGE      = 6;
constexpr int STAGE_BYTES = 32768;
constexpr int NTHREADS    = 288;
constexpr int NCONS       = 256;

constexpr int OFF_RING = 0;
constexpr int OFF_XS   = NSTAGE * STAGE_BYTES;
constexpr int XS_PITCH = 1032;
constexpr int OFF_YS   = OFF_XS + 4 * XS_PITCH * 2;
constexpr int ZO_PITCH = 520;
constexpr int ZH_PITCH = 456;
constexpr int OFF_RED  = OFF_YS + 4 * XS_PITCH * 2;
constexpr int OFF_QS   = OFF_RED + 8192;
constexpr int QS_PITCH = 136;
constexpr int OFF_ML   = OFF_QS + 8 * QS_PITCH * 2;
constexpr int OFF_BAR  = OFF_ML + 512;
constexpr int OFF_MISC = OFF_BAR + 128;
constexpr int SMEM_USED = OFF_MISC + 64;
constexpr int SMEM_BYTES = SMEM_USED + 1024;

__device__ unsigned int       g_epoch;
__device__ unsigned long long g_qx[4 * 2048];
__device__ unsigned long long g_px[NCTA * 8 * 132];
__device__ unsigned long long g_ox[4 * 2048];
__device__ unsigned long long g_hx[4 * 1792];
__device__ unsigned long long g_fx[NCTA * 256];
#define TSTAMP(i) do {} while (0)

__device__ __forceinline__ uint32_t smem_u32(const void* p) { return (uint32_t)__cvta_generic_to_shared(p); }

__device__ __forceinline__ void mbar_init(uint32_t a, uint32_t cnt) {
    asm volatile("mbarrier.init.shared::cta.b64 [%0], %1;" ::"r"(a), "r"(cnt) : "memory");
}
__device__ __forceinline__ void mbar_expect_tx(uint32_t a, uint32_t bytes) {
    asm volatile("mbarrier.arrive.expect_tx.shared::cta.b64 _, [%0], %1;" ::"r"(a), "r"(bytes) : "memory");
}
__device__ __forceinline__ void mbar_arrive(uint32_t a) {
    asm volatile("mbarrier.arrive.shared::cta.b64 _, [%0];" ::"r"(a) : "memory");
}
__device__ __forceinline__ bool mbar_try(uint32_t a, uint32_t parity) {
    uint32_t ok;
    asm volatile("{\n.reg .pred P;\nmbarrier.try_wait.parity.shared::cta.b64 P, [%1], %2;\nselp.u32 %0, 1, 0, P;\n}"
                 : "=r"(ok) : "r"(a), "r"(parity) : "memory");
    return ok != 0;
}
__device__ __forceinline__ void mbar_wait(uint32_t a, uint32_t parity) {
    uint32_t spins = 0;
    while (!mbar_try(a, parity)) {
        if (++spins > (1u << 24)) __trap();
    }
}
__device__ __forceinline__ void tma2d(uint32_t dst, const CUtensorMap* map, int c0, int c1, uint32_t bar) {
    asm volatile("cp.async.bulk.tensor.2d.shared::cluster.global.mbarrier::complete_tx::bytes [%0], [%1, {%3, %4}], [%2];"
                 ::"r"(dst), "l"(reinterpret_cast<uint64_t>(map)), "r"(bar), "r"(c0), "r"(c1) : "memory");
}
__device__ __forceinline__ void ldsm4(uint32_t (&r)[4], uint32_t addr) {
    asm volatile("ldmatrix.sync.aligned.m8n8.x4.shared.b16 {%0,%1,%2,%3}, [%4];"
                 : "=r"(r[0]), "=r"(r[1]), "=r"(r[2]), "=r"(r[3]) : "r"(addr) : "memory");
}
__device__ __forceinline__ void ldsm4t(uint32_t (&r)[4], uint32_t addr) {
    asm volatile("ldmatrix.sync.aligned.m8n8.x4.trans.shared.b16 {%0,%1,%2,%3}, [%4];"
                 : "=r"(r[0]), "=r"(r[1]), "=r"(r[2]), "=r"(r[3]) : "r"(addr) : "memory");
}
__device__ __forceinline__ void mma16816(float (&c)[4], const uint32_t (&a)[4], uint32_t b0, uint32_t b1) {
    asm volatile("mma.sync.aligned.m16n8k16.row.col.f32.bf16.bf16.f32 {%0,%1,%2,%3}, {%4,%5,%6,%7}, {%8,%9}, {%0,%1,%2,%3};"
                 : "+f"(c[0]), "+f"(c[1]), "+f"(c[2]), "+f"(c[3])
                 : "r"(a[0]), "r"(a[1]), "r"(a[2]), "r"(a[3]), "r"(b0), "r"(b1));
}
__device__ __forceinline__ uint32_t movtrans(uint32_t a) {
    uint32_t d;
    asm volatile("movmatrix.sync.aligned.m8n8.trans.b16 %0, %1;" : "=r"(d) : "r"(a));
    return d;
}
__device__ __forceinline__ uint32_t pack_bf16(float lo, float hi) {
    __nv_bfloat162 v = __floats2bfloat162_rn(lo, hi);
    return *reinterpret_cast<uint32_t*>(&v);
}
__device__ __forceinline__ void cons_sync() { asm volatile("bar.sync 1, 256;" ::: "memory"); }

__device__ __forceinline__ unsigned long long mkpkt(uint32_t data, uint32_t tag) {
    return ((unsigned long long)tag << 32) | data;
}
__device__ __forceinline__ void st_pkt(unsigned long long* p, unsigned long long v) {
    asm volatile("st.relaxed.gpu.global.b64 [%0], %1;" ::"l"(p), "l"(v) : "memory");
}
__device__ __forceinline__ void st_pkt2(unsigned long long* p, unsigned long long v0, unsigned long long v1) {
    asm volatile("st.relaxed.gpu.global.v2.b64 [%0], {%1, %2};" ::"l"(p), "l"(v0), "l"(v1) : "memory");
}
__device__ __forceinline__ unsigned long long ld_pkt(const unsigned long long* p) {
    unsigned long long v;
    asm volatile("ld.relaxed.gpu.global.b64 %0, [%1];" : "=l"(v) : "l"(p) : "memory");
    return v;
}
__device__ __forceinline__ void ld_pkt2(const unsigned long long* p, unsigned long long& v0, unsigned long long& v1) {
    asm volatile("ld.relaxed.gpu.global.v2.b64 {%0, %1}, [%2];" : "=l"(v0), "=l"(v1) : "l"(p) : "memory");
}
constexpr uint32_t SPIN_LIMIT = 1u << 18;

__device__ __forceinline__ uint2 poll2(const unsigned long long* p, uint32_t tag) {
    unsigned long long a, b;
    uint32_t spins = 0;
    while (true) {
        ld_pkt2(p, a, b);
        if ((uint32_t)(a >> 32) == tag && (uint32_t)(b >> 32) == tag) break;
        if (++spins > SPIN_LIMIT) __trap();
    }
    return make_uint2((uint32_t)a, (uint32_t)b);
}

__device__ __forceinline__ float bf_lo(uint32_t v) { return __uint_as_float(v << 16); }
__device__ __forceinline__ float bf_hi(uint32_t v) { return __uint_as_float(v & 0xffff0000u); }

__device__ __forceinline__ void gemv32_tile(float (&acc)[2][4], uint32_t base, const __nv_bfloat16* zs, int zpitch,
                                            int krow0, int w, int lane) {
    const int g = lane >> 2, t = lane & 3, i = lane >> 3;
#pragma unroll
    for (int kk = 0; kk < 4; kk++) {
        const int ks = w * 4 + kk;
        const int rib = (ks & 15) * 16 + (i >> 1) * 8 + (lane & 7);
        const uint32_t rowaddr = base + (ks >> 4) * 16384 + rib * 64;
        uint32_t b0 = 0, b1 = 0;
        if (g < 4) {
            const uint32_t* zp = reinterpret_cast<const uint32_t*>(zs + g * zpitch + krow0 + ks * 16 + 2 * t);
            b0 = zp[0];
            b1 = zp[4];
        }
#pragma unroll
        for (int mt = 0; mt < 2; mt++) {
            uint32_t a[4];
            const int chunk = mt * 2 + (i & 1);
            ldsm4t(a, rowaddr + ((chunk ^ ((rib >> 1) & 3)) << 4));
            mma16816(acc[mt], a, b0, b1);
        }
    }
}

template <int NKS>
__device__ __forceinline__ void gemv64_tile(float (&acc)[4][4], uint32_t base, const __nv_bfloat16* zs, int zpitch,
                                            int krow0, int w, int lane) {
    const int g = lane >> 2, t = lane & 3, i = lane >> 3;
#pragma unroll
    for (int kk = 0; kk < 2; kk++) {
        const int ks = w + kk * 8;
        if (ks < NKS) {
            const int row = ks * 16 + (i >> 1) * 8 + (lane & 7);
            const uint32_t rowaddr = base + row * 128;
            uint32_t b0 = 0, b1 = 0;
            if (g < 4) {
                const uint32_t* zp = reinterpret_cast<const uint32_t*>(zs + g * zpitch + krow0 + ks * 16 + 2 * t);
                b0 = zp[0];
                b1 = zp[4];
            }
#pragma unroll
            for (int mt = 0; mt < 4; mt++) {
                uint32_t a[4];
                const int chunk = mt * 2 + (i & 1);
                ldsm4t(a, rowaddr + ((chunk ^ (row & 7)) << 4));
                mma16816(acc[mt], a, b0, b1);
            }
        }
    }
}

__global__ void __launch_bounds__(NTHREADS, 1)
fused_decode_kernel(const __grid_constant__ CUtensorMap tm_wq, const __grid_constant__ CUtensorMap tm_w1,
                    const __grid_constant__ CUtensorMap tm_k, const __grid_constant__ CUtensorMap tm_v,
                    const __grid_constant__ CUtensorMap tm_w2, const __grid_constant__ CUtensorMap tm_wo,
                    const __nv_bfloat16* __restrict__ x, const __nv_bfloat16* __restrict__ b1,
                    const __nv_bfloat16* __restrict__ b2, const __nv_bfloat16* __restrict__ gate_w,
                    __nv_bfloat16* __restrict__ out) {
    extern __shared__ unsigned char smem_raw[];
    const uint32_t raw_addr = smem_u32(smem_raw);
    const uint32_t pad = (1024 - (raw_addr & 1023)) & 1023;
    unsigned char* sm = smem_raw + pad;
    const uint32_t sbase = raw_addr + pad;

    const int tid = threadIdx.x, w = tid >> 5, lane = tid & 31;
    const int c = blockIdx.x;
    const int hkv = c >> 5, bb = (c >> 3) & 3, sp = c & 7;
    const int fj = c & 15, fr = c >> 4;
    const bool has_w1 = c < 112;

    const uint32_t bar_full = sbase + OFF_BAR, bar_empty = sbase + OFF_BAR + 8 * NSTAGE;

    if (w == 8) {
        if (lane == 0) {
            for (int s = 0; s < NSTAGE; s++) {
                mbar_init(bar_full + 8 * s, 1);
                mbar_init(bar_empty + 8 * s, 8);
            }
            asm volatile("fence.mbarrier_init.release.cluster;" ::: "memory");
            asm volatile("fence.proxy.async.shared::cta;" ::: "memory");
        }
        int n = 0;
        const int kvrow0 = (bb * 4 + hkv) * 8192 + sp * 1024;
        const int nslots = has_w1 ? 25 : 23;
        auto issue = [&](int slot) {
            const int s = slot % NSTAGE;
            const uint32_t dst = sbase + OFF_RING + s * STAGE_BYTES;
            const uint32_t fb = bar_full + 8 * s;
            int id = slot;
            if (!has_w1 && id >= 2) id += 2;
            if (id < 2) {
                mbar_expect_tx(fb, 32768);
                tma2d(dst, &tm_wq, c * 32, id * 512, fb);
                tma2d(dst + 16384, &tm_wq, c * 32, id * 512 + 256, fb);
            } else if (id < 4) {
                mbar_expect_tx(fb, 32768);
                tma2d(dst, &tm_w1, c * 32, (id - 2) * 512, fb);
                tma2d(dst + 16384, &tm_w1, c * 32, (id - 2) * 512 + 256, fb);
            } else if (id < 20) {
                const int it = (id - 4) >> 1;
                const CUtensorMap* m = ((id - 4) & 1) ? &tm_v : &tm_k;
                mbar_expect_tx(fb, 32768);
                tma2d(dst, m, 0, kvrow0 + it * 128, fb);
                tma2d(dst + 16384, m, 64, kvrow0 + it * 128, fb);
            } else if (id == 20) {
                mbar_arrive(fb);
            } else if (id < 23) {
                mbar_expect_tx(fb, 224 * 128);
                tma2d(dst, &tm_w2, fj * 64, fr * 448 + (id - 21) * 224, fb);
            } else {
                mbar_expect_tx(fb, 32768);
                tma2d(dst, &tm_wo, fj * 64, fr * 512 + (id - 23) * 256, fb);
            }
        };
        if (lane == 0) {
            for (; n < NSTAGE; n++) issue(n);
        }
        __syncthreads();
        if (lane == 0) {
            for (; n < nslots; n++) {
                mbar_wait(bar_empty + 8 * (n % NSTAGE), ((n / NSTAGE) - 1) & 1);
                issue(n);
            }
        }
        return;
    }

    TSTAMP(0);
    __nv_bfloat16* xs = reinterpret_cast<__nv_bfloat16*>(sm + OFF_XS);
    __nv_bfloat16* ys = reinterpret_cast<__nv_bfloat16*>(sm + OFF_YS);
    __nv_bfloat16* zo = xs;
    __nv_bfloat16* zh = ys;
    float* red = reinterpret_cast<float*>(sm + OFF_RED);
    __nv_bfloat16* qs = reinterpret_cast<__nv_bfloat16*>(sm + OFF_QS);
    float2* ml = reinterpret_cast<float2*>(sm + OFF_ML);
    float* s_gate = reinterpret_cast<float*>(sm + OFF_MISC);
    uint32_t* s_tag = reinterpret_cast<uint32_t*>(sm + OFF_MISC + 16);
    const int g = lane >> 2, t = lane & 3;

    float b1v0 = 0.f, b1v1 = 0.f, b2v = 0.f;
    if (has_w1 && tid < 64) {
        uint32_t v = *reinterpret_cast<const uint32_t*>(b1 + c * 32 + (tid & 15) * 2);
        b1v0 = bf_lo(v);
        b1v1 = bf_hi(v);
    }
    b2v = __bfloat162float(b2[fj * 64 + fr * 8 + (tid >> 5)]);

    {
        const int row = w & 3;
        uint4 v[4];
#pragma unroll
        for (int i = 0; i < 4; i++)
            v[i] = *reinterpret_cast<const uint4*>(x + row * 1024 + (i * 32 + lane) * 8);
        if (tid == 0) {
            unsigned e;
            asm volatile("ld.relaxed.gpu.global.u32 %0, [%1];" : "=r"(e) : "l"(&g_epoch) : "memory");
            *s_tag = e + 1;
        }
        float f[32];
#pragma unroll
        for (int i = 0; i < 4; i++) {
            f[i * 8 + 0] = bf_lo(v[i].x); f[i * 8 + 1] = bf_hi(v[i].x);
            f[i * 8 + 2] = bf_lo(v[i].y); f[i * 8 + 3] = bf_hi(v[i].y);
            f[i * 8 + 4] = bf_lo(v[i].z); f[i * 8 + 5] = bf_hi(v[i].z);
            f[i * 8 + 6] = bf_lo(v[i].w); f[i * 8 + 7] = bf_hi(v[i].w);
        }
        if (w < 4) {
            float s = 0.f;
#pragma unroll
            for (int i = 0; i < 32; i++) s += f[i];
#pragma unroll
            for (int o = 16; o > 0; o >>= 1) s += __shfl_xor_sync(0xffffffffu, s, o);
            const float mean = s * (1.0f / 1024.0f);
            float q = 0.f;
#pragma unroll
            for (int i = 0; i < 32; i++) { float d = f[i] - mean; q += d * d; }
#pragma unroll
            for (int o = 16; o > 0; o >>= 1) q += __shfl_xor_sync(0xffffffffu, q, o);
            const float rstd = 1.0f / sqrtf(q * (1.0f / 1024.0f) + 1e-5f);
#pragma unroll
            for (int i = 0; i < 4; i++) {
                *reinterpret_cast<uint4*>(xs + row * XS_PITCH + (i * 32 + lane) * 8) = v[i];
                uint4 y;
                y.x = pack_bf16((f[i * 8 + 0] - mean) * rstd, (f[i * 8 + 1] - mean) * rstd);
                y.y = pack_bf16((f[i * 8 + 2] - mean) * rstd, (f[i * 8 + 3] - mean) * rstd);
                y.z = pack_bf16((f[i * 8 + 4] - mean) * rstd, (f[i * 8 + 5] - mean) * rstd);
                y.w = pack_bf16((f[i * 8 + 6] - mean) * rstd, (f[i * 8 + 7] - mean) * rstd);
                *reinterpret_cast<uint4*>(ys + row * XS_PITCH + (i * 32 + lane) * 8) = y;
            }
        } else {
            float s = 0.f;
#pragma unroll
            for (int i = 0; i < 4; i++) {
                uint4 gw = *reinterpret_cast<const uint4*>(gate_w + (i * 32 + lane) * 8);
                s += f[i * 8 + 0] * bf_lo(gw.x) + f[i * 8 + 1] * bf_hi(gw.x);
                s += f[i * 8 + 2] * bf_lo(gw.y) + f[i * 8 + 3] * bf_hi(gw.y);
                s += f[i * 8 + 4] * bf_lo(gw.z) + f[i * 8 + 5] * bf_hi(gw.z);
                s += f[i * 8 + 6] * bf_lo(gw.w) + f[i * 8 + 7] * bf_hi(gw.w);
            }
#pragma unroll
            for (int o = 16; o > 0; o >>= 1) s += __shfl_xor_sync(0xffffffffu, s, o);
            if (lane == 0) s_gate[row] = 1.0f / (1.0f + __expf(-s));
        }
    }
    __syncthreads();
    const uint32_t tag = *s_tag;
    TSTAMP(1);

    int n = 0;
    auto wait_full = [&](int slot) -> uint32_t {
        const int s = slot % NSTAGE;
        mbar_wait(bar_full + 8 * s, (slot / NSTAGE) & 1);
        return sbase + OFF_RING + s * STAGE_BYTES;
    };
    auto release = [&](int slot) {
        __syncwarp();
        if (lane == 0) mbar_arrive(bar_empty + 8 * (slot % NSTAGE));
    };

    {
        float acc[2][4] = {};
#pragma unroll
        for (int tl = 0; tl < 2; tl++) {
            const uint32_t base = wait_full(n);
            gemv32_tile(acc, base, xs, XS_PITCH, tl * 512, w, lane);
            release(n);
            n++;
        }
        if (t < 2) {
#pragma unroll
            for (int mt = 0; mt < 2; mt++) {
                *reinterpret_cast<float2*>(red + (w * 32 + mt * 16 + g) * 4 + 2 * t) = make_float2(acc[mt][0], acc[mt][1]);
                *reinterpret_cast<float2*>(red + (w * 32 + mt * 16 + g + 8) * 4 + 2 * t) = make_float2(acc[mt][2], acc[mt][3]);
            }
        }
        cons_sync();
        if (tid < 64) {
            const int b = tid >> 4, cp = tid & 15;
            float s0 = 0.f, s1 = 0.f;
#pragma unroll
            for (int ww = 0; ww < 8; ww++) {
                s0 += red[(ww * 32 + cp * 2) * 4 + b];
                s1 += red[(ww * 32 + cp * 2 + 1) * 4 + b];
            }
            st_pkt(&g_qx[b * 2048 + c * 16 + cp], mkpkt(pack_bf16(s0, s1), tag));
        }
    }
    TSTAMP(2);
    if (has_w1) {
        float* red2 = red + 1024;
        float acc[2][4] = {};
#pragma unroll
        for (int tl = 0; tl < 2; tl++) {
            const uint32_t base = wait_full(n);
            gemv32_tile(acc, base, ys, XS_PITCH, tl * 512, w, lane);
            release(n);
            n++;
        }
        if (t < 2) {
#pragma unroll
            for (int mt = 0; mt < 2; mt++) {
                *reinterpret_cast<float2*>(red2 + (w * 32 + mt * 16 + g) * 4 + 2 * t) = make_float2(acc[mt][0], acc[mt][1]);
                *reinterpret_cast<float2*>(red2 + (w * 32 + mt * 16 + g + 8) * 4 + 2 * t) = make_float2(acc[mt][2], acc[mt][3]);
            }
        }
        cons_sync();
        if (tid < 64) {
            const int b = tid >> 4, cp = tid & 15;
            float s0 = b1v0, s1 = b1v1;
#pragma unroll
            for (int ww = 0; ww < 8; ww++) {
                s0 += red2[(ww * 32 + cp * 2) * 4 + b];
                s1 += red2[(ww * 32 + cp * 2 + 1) * 4 + b];
            }
            const float k0 = 0.7978845608028654f, k1 = 0.044715f;
            const float h0 = 0.5f * s0 * (1.0f + tanhf(k0 * (s0 + k1 * s0 * s0 * s0)));
            const float h1 = 0.5f * s1 * (1.0f + tanhf(k0 * (s1 + k1 * s1 * s1 * s1)));
            st_pkt(&g_hx[b * 1792 + c * 16 + cp], mkpkt(pack_bf16(h0, h1), tag));
        }
    }
    TSTAMP(3);
    uint32_t qf[8][2];
    {
        uint2 v = poll2(&g_qx[bb * 2048 + hkv * 512 + 2 * tid], tag);
        *reinterpret_cast<uint2*>(qs + (tid >> 5) * QS_PITCH + (tid & 31) * 4) = v;
        cons_sync();
#pragma unroll
        for (int ks = 0; ks < 8; ks++) {
            const uint32_t* qp = reinterpret_cast<const uint32_t*>(qs + g * QS_PITCH + ks * 16 + 2 * t);
            qf[ks][0] = qp[0];
            qf[ks][1] = qp[4];
        }
    }
    TSTAMP(4);
    const float sc = 0.08838834764831845f * 1.4426950408889634f;
    float o[8][4];
#pragma unroll
    for (int i = 0; i < 8; i++) { o[i][0] = o[i][1] = o[i][2] = o[i][3] = 0.f; }
    float m0 = -INFINITY, m1 = -INFINITY, l0 = 0.f, l1 = 0.f;
    {
        const int krow = w * 16 + (lane & 7) + ((lane >> 3) & 1) * 8;
        const uint32_t koff = krow * 128;
        const int kx = krow & 7, kc = lane >> 4;
        const int vrow = w * 16 + (lane & 7) + (lane >> 4) * 8;
        const uint32_t voff = vrow * 128;
        const int vx = vrow & 7, vc = (lane >> 3) & 1;
#pragma unroll 1
        for (int it = 0; it < 8; it++) {
            const uint32_t kb = wait_full(n);
            float s0[4] = {0.f, 0.f, 0.f, 0.f}, s1[4] = {0.f, 0.f, 0.f, 0.f};
#pragma unroll
            for (int k4 = 0; k4 < 4; k4++) {
                uint32_t a[4], a2[4];
                const uint32_t sw = ((k4 * 2 + kc) ^ kx) << 4;
                ldsm4(a, kb + koff + sw);
                ldsm4(a2, kb + 16384 + koff + sw);
                mma16816(s0, a, qf[k4][0], qf[k4][1]);
                mma16816(s1, a2, qf[4 + k4][0], qf[4 + k4][1]);
            }
            release(n);
            n++;
            const float c0 = s0[0] + s1[0], c1 = s0[1] + s1[1], c2 = s0[2] + s1[2], c3 = s0[3] + s1[3];
            float mx0 = fmaxf(c0, c2), mx1 = fmaxf(c1, c3);
#pragma unroll
            for (int off = 4; off < 32; off <<= 1) {
                mx0 = fmaxf(mx0, __shfl_xor_sync(0xffffffffu, mx0, off));
                mx1 = fmaxf(mx1, __shfl_xor_sync(0xffffffffu, mx1, off));
            }
            const float mn0 = fmaxf(m0, mx0), mn1 = fmaxf(m1, mx1);
            const float f0 = exp2f((m0 - mn0) * sc), f1 = exp2f((m1 - mn1) * sc);
            m0 = mn0; m1 = mn1;
            const float ms0 = mn0 * sc, ms1 = mn1 * sc;
            const float p0 = exp2f(fmaf(c0, sc, -ms0)), p1 = exp2f(fmaf(c1, sc, -ms1));
            const float p2 = exp2f(fmaf(c2, sc, -ms0)), p3 = exp2f(fmaf(c3, sc, -ms1));
            l0 = l0 * f0 + p0 + p2;
            l1 = l1 * f1 + p1 + p3;
            const uint32_t pb0 = movtrans(pack_bf16(p0, p1));
            const uint32_t pb1 = movtrans(pack_bf16(p2, p3));
#pragma unroll
            for (int i = 0; i < 8; i++) { o[i][0] *= f0; o[i][1] *= f1; o[i][2] *= f0; o[i][3] *= f1; }
            const uint32_t vb = wait_full(n);
#pragma unroll
            for (int mt = 0; mt < 8; mt++) {
                uint32_t a[4];
                ldsm4t(a, vb + (mt >> 2) * 16384 + voff + ((((mt & 3) * 2 + vc) ^ vx) << 4));
                mma16816(o[mt], a, pb0, pb1);
            }
            release(n);
            n++;
        }
    }
    TSTAMP(5);
    {
        const uint32_t sb = wait_full(n);
        float* scr = reinterpret_cast<float*>(sm + (sb - sbase));
#pragma unroll
        for (int off = 4; off < 32; off <<= 1) {
            l0 += __shfl_xor_sync(0xffffffffu, l0, off);
            l1 += __shfl_xor_sync(0xffffffffu, l1, off);
        }
        if (g == 0) {
            ml[w * 8 + 2 * t] = make_float2(m0, l0);
            ml[w * 8 + 2 * t + 1] = make_float2(m1, l1);
        }
        float* sw = scr + w * 1024;
#pragma unroll
        for (int mt = 0; mt < 8; mt++) {
            const int d0 = (mt * 16 + g) ^ (t << 3), d1 = (mt * 16 + g + 8) ^ (t << 3);
            sw[(2 * t) * 128 + d0] = o[mt][0];
            sw[(2 * t + 1) * 128 + d0] = o[mt][1];
            sw[(2 * t) * 128 + d1] = o[mt][2];
            sw[(2 * t + 1) * 128 + d1] = o[mt][3];
        }
        cons_sync();
        const int head = w;
        float M = -INFINITY;
#pragma unroll
        for (int ww = 0; ww < 8; ww++) M = fmaxf(M, ml[ww * 8 + head].x);
        float L = 0.f;
        float4 acc = make_float4(0.f, 0.f, 0.f, 0.f);
        const int d4 = (lane * 4) ^ ((head >> 1) << 3);
#pragma unroll
        for (int ww = 0; ww < 8; ww++) {
            const float2 v = ml[ww * 8 + head];
            const float f = exp2f((v.x - M) * sc);
            L += f * v.y;
            const float4 ov = *reinterpret_cast<const float4*>(scr + ww * 1024 + head * 128 + d4);
            acc.x += f * ov.x; acc.y += f * ov.y; acc.z += f * ov.z; acc.w += f * ov.w;
        }
        unsigned long long* dst = &g_px[(c * 8 + head) * 132];
        st_pkt2(dst + lane * 4, mkpkt(__float_as_uint(acc.x), tag), mkpkt(__float_as_uint(acc.y), tag));
        st_pkt2(dst + lane * 4 + 2, mkpkt(__float_as_uint(acc.z), tag), mkpkt(__float_as_uint(acc.w), tag));
        if (lane == 0) st_pkt2(dst + 128, mkpkt(__float_as_uint(M), tag), mkpkt(__float_as_uint(L), tag));
        asm volatile("fence.proxy.async.shared::cta;" ::: "memory");
        release(n);
        n++;
    }
    TSTAMP(6);
    if (w < 4) {
        const unsigned long long* src = &g_px[((c & ~7) * 8 + sp) * 132];
        unsigned long long pv[8], pm[8], pl[8];
        uint32_t spins = 0;
        while (true) {
            bool ok = true;
#pragma unroll
            for (int s = 0; s < 8; s++) {
                pv[s] = ld_pkt(src + s * 8 * 132 + tid);
                ld_pkt2(src + s * 8 * 132 + 128, pm[s], pl[s]);
            }
#pragma unroll
            for (int s = 0; s < 8; s++)
                ok = ok && ((uint32_t)(pv[s] >> 32) == tag) && ((uint32_t)(pm[s] >> 32) == tag) && ((uint32_t)(pl[s] >> 32) == tag);
            if (ok) break;
            if (++spins > SPIN_LIMIT) __trap();
        }
        float M = -INFINITY;
#pragma unroll
        for (int s = 0; s < 8; s++) M = fmaxf(M, __uint_as_float((uint32_t)pm[s]));
        float L = 0.f, ov = 0.f;
#pragma unroll
        for (int s = 0; s < 8; s++) {
            const float f = exp2f((__uint_as_float((uint32_t)pm[s]) - M) * sc);
            L += f * __uint_as_float((uint32_t)pl[s]);
            ov += f * __uint_as_float((uint32_t)pv[s]);
        }
        ov = ov / L;
        __syncwarp();
        const float nb = __shfl_down_sync(0xffffffffu, ov, 1);
        if (!(lane & 1))
            st_pkt(&g_ox[bb * 2048 + (hkv * 8 + sp) * 64 + (tid >> 1)], mkpkt(pack_bf16(ov, nb), tag));
    } else {
#pragma unroll
        for (int k = 0; k < 4; k++) {
            const int idx = tid - 128 + 128 * k;
            if (idx < 448) {
                const int b = idx / 112, p = idx % 112;
                uint2 v = poll2(&g_hx[b * 1792 + fr * 224 + 2 * p], tag);
                *reinterpret_cast<uint2*>(zh + b * ZH_PITCH + 4 * p) = v;
            }
        }
    }
    cons_sync();
    TSTAMP(7);
    float acch[4][4] = {}, acco[4][4] = {};
#pragma unroll
    for (int tl = 0; tl < 2; tl++) {
        const uint32_t base = wait_full(n);
        gemv64_tile<14>(acch, base, zh, ZH_PITCH, tl * 224, w, lane);
        release(n);
        n++;
    }
    TSTAMP(8);
#pragma unroll
    for (int k = 0; k < 2; k++) {
        const int idx = tid + 256 * k;
        const int b = idx >> 7, p = idx & 127;
        uint2 v = poll2(&g_ox[b * 2048 + fr * 256 + 2 * p], tag);
        *reinterpret_cast<uint2*>(zo + b * ZO_PITCH + 4 * p) = v;
    }
    cons_sync();
    TSTAMP(9);
#pragma unroll
    for (int tl = 0; tl < 2; tl++) {
        const uint32_t base = wait_full(n);
        gemv64_tile<16>(acco, base, zo, ZO_PITCH, tl * 256, w, lane);
        n++;
    }
    TSTAMP(10);
    if (t < 2) {
        const float ga = s_gate[2 * t], gb = s_gate[2 * t + 1];
#pragma unroll
        for (int mt = 0; mt < 4; mt++) {
            *reinterpret_cast<float2*>(red + (w * 64 + mt * 16 + g) * 4 + 2 * t) =
                make_float2(ga * acco[mt][0] + (1.0f - ga) * acch[mt][0], gb * acco[mt][1] + (1.0f - gb) * acch[mt][1]);
            *reinterpret_cast<float2*>(red + (w * 64 + mt * 16 + g + 8) * 4 + 2 * t) =
                make_float2(ga * acco[mt][2] + (1.0f - ga) * acch[mt][2], gb * acco[mt][3] + (1.0f - gb) * acch[mt][3]);
        }
    }
    cons_sync();
    {
        float s = 0.f;
#pragma unroll
        for (int ww = 0; ww < 8; ww++) s += red[ww * 256 + tid];
        st_pkt(&g_fx[c * 256 + tid], mkpkt(__float_as_uint(s), tag));
    }
    TSTAMP(11);
    {
        const int s = tid & 7, oidx = tid >> 3;
        const unsigned long long* p = &g_fx[(s * 16 + fj) * 256 + fr * 32 + oidx];
        unsigned long long v;
        uint32_t spins = 0;
        while (true) {
            v = ld_pkt(p);
            if ((uint32_t)(v >> 32) == tag) break;
            if (++spins > SPIN_LIMIT) __trap();
        }
        float f = __uint_as_float((uint32_t)v);
        __syncwarp();
        f += __shfl_xor_sync(0xffffffffu, f, 1);
        f += __shfl_xor_sync(0xffffffffu, f, 2);
        f += __shfl_xor_sync(0xffffffffu, f, 4);
        if (s == 0) {
            const int b = oidx & 3, col8 = oidx >> 2;
            const float r = f + (1.0f - s_gate[b]) * b2v;
            out[b * 1024 + fj * 64 + fr * 8 + col8] = __float2bfloat16(r);
        }
        if (c == 0 && tid == 0) {
            asm volatile("st.relaxed.gpu.global.u32 [%0], %1;" ::"l"(&g_epoch), "r"(tag) : "memory");
        }
    }
    TSTAMP(12);
}

typedef CUresult (*EncodeFn)(CUtensorMap*, CUtensorMapDataType, cuuint32_t, void*, const cuuint64_t*, const cuuint64_t*,
                             const cuuint32_t*, const cuuint32_t*, CUtensorMapInterleave, CUtensorMapSwizzle,
                             CUtensorMapL2promotion, CUtensorMapFloatOOBfill);

void make_map(EncodeFn fn, CUtensorMap* m, const void* ptr, uint64_t inner, uint64_t rows, uint32_t box_inner,
              uint32_t box_rows, CUtensorMapSwizzle sw, CUtensorMapL2promotion prom) {
    cuuint64_t dims[2] = {inner, rows};
    cuuint64_t strides[1] = {inner * 2};
    cuuint32_t box[2] = {box_inner, box_rows};
    cuuint32_t estr[2] = {1, 1};
    fn(m, CU_TENSOR_MAP_DATA_TYPE_BFLOAT16, 2, const_cast<void*>(ptr), dims, strides, box, estr,
       CU_TENSOR_MAP_INTERLEAVE_NONE, sw, prom, CU_TENSOR_MAP_FLOAT_OOB_FILL_NONE);
}

}

extern "C" void kernel_launch(void* const* d_in, const int* in_sizes, int n_in, void* d_out, int out_size) {
    (void)in_sizes; (void)n_in; (void)out_size;
    static EncodeFn fn = nullptr;
    if (!fn) {
        void* p = nullptr;
        cudaDriverEntryPointQueryResult st;
        cudaGetDriverEntryPoint("cuTensorMapEncodeTiled", &p, cudaEnableDefault, &st);
        fn = (EncodeFn)p;
        cudaFuncSetAttribute(fused_decode_kernel, cudaFuncAttributeMaxDynamicSharedMemorySize, SMEM_BYTES);
    }
    const __nv_bfloat16* x  = (const __nv_bfloat16*)d_in[0];
    const void* kc = d_in[1];
    const void* vc = d_in[2];
    const void* wq = d_in[3];
    const void* wo = d_in[4];
    const void* w1 = d_in[6];
    const __nv_bfloat16* b1 = (const __nv_bfloat16*)d_in[7];
    const void* w2 = d_in[8];
    const __nv_bfloat16* b2 = (const __nv_bfloat16*)d_in[9];
    const __nv_bfloat16* gw = (const __nv_bfloat16*)d_in[10];

    CUtensorMap m_wq, m_w1, m_k, m_v, m_w2, m_wo;
    make_map(fn, &m_wq, wq, 4096, 1024, 32, 256, CU_TENSOR_MAP_SWIZZLE_64B, CU_TENSOR_MAP_L2_PROMOTION_L2_256B);
    make_map(fn, &m_w1, w1, 3584, 1024, 32, 256, CU_TENSOR_MAP_SWIZZLE_64B, CU_TENSOR_MAP_L2_PROMOTION_L2_256B);
    make_map(fn, &m_k, kc, 128, 131072, 64, 128, CU_TENSOR_MAP_SWIZZLE_128B, CU_TENSOR_MAP_L2_PROMOTION_L2_256B);
    make_map(fn, &m_v, vc, 128, 131072, 64, 128, CU_TENSOR_MAP_SWIZZLE_128B, CU_TENSOR_MAP_L2_PROMOTION_L2_256B);
    make_map(fn, &m_w2, w2, 1024, 3584, 64, 224, CU_TENSOR_MAP_SWIZZLE_128B, CU_TENSOR_MAP_L2_PROMOTION_L2_256B);
    make_map(fn, &m_wo, wo, 1024, 4096, 64, 256, CU_TENSOR_MAP_SWIZZLE_128B, CU_TENSOR_MAP_L2_PROMOTION_L2_256B);

    fused_decode_kernel<<<NCTA, NTHREADS, SMEM_BYTES>>>(m_wq, m_w1, m_k, m_v, m_w2, m_wo, x, b1, b2, gw,
                                                        (__nv_bfloat16*)d_out);
}
```

```cpp
#include <cuda_runtime.h>
#include <cuda_bf16.h>
#include <cuda.h>
#include <stdint.h>

namespace {

constexpr int NCTA     = 128;
constexpr int NSTAGE   = 12;
constexpr int SLOT     = 16384;
constexpr int NTHREADS = 320;
#define PACE_G 128
#define PACE_OFF 64
#define PACE_END 50
#define PACE_SYM 38
#define PACE_T1 128
#define PACE_T2 256
#define PACE_START 6
#define PACE_SLEEP 100
#define PACE_MAX 2
#define DEPTH_ 4
#define TAIL_AT 38
#define DEPTH_TAIL 3
#define TAIL2_AT 46
#define DEPTH_TAIL2 2
#define PW_IT 3
#define PXWAIT 2
#define PXWAIT_L PXWAIT
#define OXWAIT 6
#define OXWAIT_L 5
#define HXWAIT 6
#define HXWAIT_L 5
#define HX_AT 4
#define QWAIT 6
#define QSLEEP 300
#define NPAIR 2
#define PROM_WQ 2
#define PROM_W1 2
#define PROM_W2 1
#define PROM_WO 2
#define PROM_KV 3
#define PROM_WP 1
#define PROD_FIRST 1
constexpr int KROWS   = (4 - NPAIR) * 256;
constexpr int PROWS   = NPAIR * 512;
constexpr int W1_ID   = 38;
constexpr int KV_ID   = 4;
constexpr int SCR_ID  = KV_ID + 32;
constexpr int DEPTH    = DEPTH_;

constexpr int VP       = 1032;
constexpr int VPO      = PROWS + KROWS + 8;
constexpr int OFF_VA   = NSTAGE * SLOT;
constexpr int OFF_VB   = OFF_VA + 4 * VPO * 2;
constexpr int OFF_RED  = OFF_VB + 4 * VP * 2;
constexpr int OFF_XB   = OFF_RED + 5120;
constexpr int OFF_QS   = OFF_XB + 1024;
constexpr int QS_PITCH = 136;
constexpr int OFF_ML   = OFF_QS + 8 * QS_PITCH * 2;
constexpr int OFF_BAR  = OFF_ML + 512;
constexpr int OFF_MISC = OFF_BAR + 256;
constexpr int SMEM_USED = OFF_MISC + 64;
constexpr int SMEM_BYTES = SMEM_USED + 1024;

__device__ unsigned int       g_epoch;
__device__ __align__(128) unsigned int g_prog;
__device__ __align__(128) unsigned long long g_qx[4 * 2048];
__device__ __align__(128) uint32_t           g_px[NCTA * 8 * 128];
__device__ __align__(128) uint32_t           g_ml[NCTA * 64];
__device__ __align__(128) unsigned long long g_ox[4 * 2048];
__device__ __align__(128) unsigned long long g_hx[4 * 1792];
__device__ __align__(128) uint32_t           g_fx[NCTA * 256];

__device__ __forceinline__ uint32_t smem_u32(const void* p) { return (uint32_t)__cvta_generic_to_shared(p); }
__device__ __forceinline__ int ltid() {
    const int p = threadIdx.x;
    return p < 32 ? p + 256 : (p < 288 ? p - 32 : p);
}

__device__ __forceinline__ void mbar_init(uint32_t a, uint32_t cnt) {
    asm volatile("mbarrier.init.shared::cta.b64 [%0], %1;" ::"r"(a), "r"(cnt) : "memory");
}
__device__ __forceinline__ void mbar_expect_tx(uint32_t a, uint32_t bytes) {
    asm volatile("mbarrier.arrive.expect_tx.shared::cta.b64 _, [%0], %1;" ::"r"(a), "r"(bytes) : "memory");
}
__device__ __forceinline__ void mbar_arrive(uint32_t a) {
    asm volatile("mbarrier.arrive.shared::cta.b64 _, [%0];" ::"r"(a) : "memory");
}
__device__ __forceinline__ bool mbar_try(uint32_t a, uint32_t parity) {
    uint32_t ok;
    asm volatile("{\n.reg .pred P;\nmbarrier.try_wait.parity.shared::cta.b64 P, [%1], %2;\nselp.u32 %0, 1, 0, P;\n}"
                 : "=r"(ok) : "r"(a), "r"(parity) : "memory");
    return ok != 0;
}
__device__ __forceinline__ bool mbar_test(uint32_t a, uint32_t parity) {
    uint32_t ok;
    asm volatile("{\n.reg .pred P;\nmbarrier.test_wait.parity.shared::cta.b64 P, [%1], %2;\nselp.u32 %0, 1, 0, P;\n}"
                 : "=r"(ok) : "r"(a), "r"(parity) : "memory");
    return ok != 0;
}
__device__ __forceinline__ bool mbar_try_cluster(uint32_t a, uint32_t parity) {
    uint32_t ok;
    asm volatile("{\n.reg .pred P;\nmbarrier.try_wait.parity.acquire.cluster.shared::cta.b64 P, [%1], %2;\nselp.u32 %0, 1, 0, P;\n}"
                 : "=r"(ok) : "r"(a), "r"(parity) : "memory");
    return ok != 0;
}
__device__ __forceinline__ void mbar_wait(uint32_t a, uint32_t parity) {
    uint32_t spins = 0;
    while (!mbar_try(a, parity)) {
        if (++spins > (1u << 18)) __trap();
    }
}
__device__ __forceinline__ uint64_t policy_evict_first() {
    uint64_t p;
    asm volatile("createpolicy.fractional.L2::evict_first.b64 %0, 1.0;" : "=l"(p));
    return p;
}
__device__ __forceinline__ void tma2d(uint32_t dst, const CUtensorMap* map, int c0, int c1, uint32_t bar, uint64_t pol) {
    asm volatile("cp.async.bulk.tensor.2d.shared::cluster.global.mbarrier::complete_tx::bytes.L2::cache_hint [%0], [%1, {%3, %4}], [%2], %5;"
                 ::"r"(dst), "l"(reinterpret_cast<uint64_t>(map)), "r"(bar), "r"(c0), "r"(c1), "l"(pol) : "memory");
}
__device__ __forceinline__ void ldsm4(uint32_t (&r)[4], uint32_t addr) {
    asm volatile("ldmatrix.sync.aligned.m8n8.x4.shared.b16 {%0,%1,%2,%3}, [%4];"
                 : "=r"(r[0]), "=r"(r[1]), "=r"(r[2]), "=r"(r[3]) : "r"(addr) : "memory");
}
__device__ __forceinline__ void ldsm4t(uint32_t (&r)[4], uint32_t addr) {
    asm volatile("ldmatrix.sync.aligned.m8n8.x4.trans.shared.b16 {%0,%1,%2,%3}, [%4];"
                 : "=r"(r[0]), "=r"(r[1]), "=r"(r[2]), "=r"(r[3]) : "r"(addr) : "memory");
}
__device__ __forceinline__ void mma16816(float (&c)[4], const uint32_t (&a)[4], uint32_t b0, uint32_t b1) {
    asm volatile("mma.sync.aligned.m16n8k16.row.col.f32.bf16.bf16.f32 {%0,%1,%2,%3}, {%4,%5,%6,%7}, {%8,%9}, {%0,%1,%2,%3};"
                 : "+f"(c[0]), "+f"(c[1]), "+f"(c[2]), "+f"(c[3])
                 : "r"(a[0]), "r"(a[1]), "r"(a[2]), "r"(a[3]), "r"(b0), "r"(b1));
}
__device__ __forceinline__ uint32_t movtrans(uint32_t a) {
    uint32_t d;
    asm volatile("movmatrix.sync.aligned.m8n8.trans.b16 %0, %1;" : "=r"(d) : "r"(a));
    return d;
}
__device__ __forceinline__ uint32_t pack_bf16(float lo, float hi) {
    __nv_bfloat162 v = __floats2bfloat162_rn(lo, hi);
    return *reinterpret_cast<uint32_t*>(&v);
}
__device__ __forceinline__ void cons_sync() { asm volatile("bar.sync 1, 256;" ::: "memory"); }

__device__ __forceinline__ unsigned long long mkpkt(uint32_t data, uint32_t tag) {
    return ((unsigned long long)tag << 32) | data;
}
__device__ __forceinline__ void st_pkt(unsigned long long* p, unsigned long long v) {
    asm volatile("st.relaxed.gpu.global.b64 [%0], %1;" ::"l"(p), "l"(v) : "memory");
}
__device__ __forceinline__ void st_pkt2(unsigned long long* p, unsigned long long v0, unsigned long long v1) {
    asm volatile("st.relaxed.gpu.global.v2.b64 [%0], {%1, %2};" ::"l"(p), "l"(v0), "l"(v1) : "memory");
}
__device__ __forceinline__ unsigned long long ld_pkt(const unsigned long long* p) {
    unsigned long long v;
    asm volatile("ld.relaxed.gpu.global.b64 %0, [%1];" : "=l"(v) : "l"(p) : "memory");
    return v;
}
__device__ __forceinline__ void ld_pkt2(const unsigned long long* p, unsigned long long& v0, unsigned long long& v1) {
    asm volatile("ld.relaxed.gpu.global.v2.b64 {%0, %1}, [%2];" : "=l"(v0), "=l"(v1) : "l"(p) : "memory");
}
__device__ __forceinline__ void st_u32(uint32_t* p, uint32_t v) {
    asm volatile("st.relaxed.gpu.global.b32 [%0], %1;" ::"l"(p), "r"(v) : "memory");
}
__device__ __forceinline__ void red_x32(uint32_t* p, uint32_t v) {
    asm volatile("red.relaxed.gpu.global.xor.b32 [%0], %1;" ::"l"(p), "r"(v) : "memory");
}
__device__ __forceinline__ void red_x64(unsigned long long* p, unsigned long long v) {
    asm volatile("red.relaxed.gpu.global.xor.b64 [%0], %1;" ::"l"(p), "l"(v) : "memory");
}
__device__ __forceinline__ uint32_t ld_u32(const uint32_t* p) {
    uint32_t v;
    asm volatile("ld.relaxed.gpu.global.b32 %0, [%1];" : "=r"(v) : "l"(p) : "memory");
    return v;
}
__device__ __forceinline__ void st_u4(uint32_t* p, uint32_t a, uint32_t b, uint32_t c, uint32_t d) {
    asm volatile("st.relaxed.gpu.global.v4.b32 [%0], {%1, %2, %3, %4};" ::"l"(p), "r"(a), "r"(b), "r"(c), "r"(d) : "memory");
}
__device__ __forceinline__ uint4 ld_u4(const uint32_t* p) {
    uint4 v;
    asm volatile("ld.relaxed.gpu.global.v4.b32 {%0, %1, %2, %3}, [%4];" : "=r"(v.x), "=r"(v.y), "=r"(v.z), "=r"(v.w) : "l"(p) : "memory");
    return v;
}
__device__ __forceinline__ uint32_t tagf(float v, uint32_t t3) { return (__float_as_uint(v) & ~7u) | t3; }
constexpr uint32_t SPIN_LIMIT = 1u << 18;
#define POLL_SLEEP 20
#define POLL_SLEEP2 20
#define FX_SLEEP0 200

__device__ __forceinline__ float bf_lo(uint32_t v) { return __uint_as_float(v << 16); }
__device__ __forceinline__ float bf_hi(uint32_t v) { return __uint_as_float(v & 0xffff0000u); }
__device__ __forceinline__ uint32_t lds32(uint32_t a) {
    uint32_t v;
    asm volatile("ld.shared.b32 %0, [%1];" : "=r"(v) : "r"(a) : "memory");
    return v;
}
__device__ __forceinline__ void sts32(uint32_t a, uint32_t v) {
    asm volatile("st.shared.b32 [%0], %1;" ::"r"(a), "r"(v) : "memory");
}
__device__ __forceinline__ void sts64(uint32_t a, uint32_t v0, uint32_t v1) {
    asm volatile("st.shared.v2.b32 [%0], {%1, %2};" ::"r"(a), "r"(v0), "r"(v1) : "memory");
}

struct Acc { float v[2][4]; };
__device__ __noinline__ Acc gemv4(uint32_t sbase, int n0, int nks, uint32_t zaddr, int ns = 4, int vp = VP) {
    const int tid = threadIdx.x - 32 * PROD_FIRST, w = (tid >> 5) & 3, lane = tid & 31;
    const int g = lane >> 2, t = lane & 3, i = lane >> 3;
    float acc[2][2][4] = {};
    const int r0 = w * 16 + (i >> 1) * 8 + (lane & 7);
    const uint32_t sw0 = (((i & 1) ^ ((r0 >> 1) & 3)) << 4), sw1 = (((2 + (i & 1)) ^ ((r0 >> 1) & 3)) << 4);
    const bool hi = w + 12 < nks;
    uint32_t b[4][4][2];
    const uint32_t zp = zaddr + ((g & 3) * vp + w * 16 + 2 * t) * 2;
#pragma unroll
    for (int j = 0; j < 4; j++) {
        const uint32_t z = zp + j * nks * 32;
#pragma unroll
        for (int kk = 0; kk < 4; kk++) {
            const bool on = (g < 4) && (kk < 3 || hi) && j < ns;
            b[j][kk][0] = on ? lds32(z + kk * 128) : 0u;
            b[j][kk][1] = on ? lds32(z + kk * 128 + 16) : 0u;
        }
    }
#pragma unroll
    for (int j = 0; j < 4; j++) {
        if (j >= ns) break;
        const int n = n0 + j;
        const int s = n % NSTAGE;
        mbar_wait(sbase + OFF_BAR + 8 * s, (n / NSTAGE) & 1);
        const uint32_t ra = sbase + s * SLOT + r0 * 64;
        uint32_t a[4][2][4];
#pragma unroll
        for (int kk = 0; kk < 4; kk++) {
            const uint32_t ko = (kk < 3 || hi) ? kk * 4096 : 0;
            ldsm4t(a[kk][0], ra + ko + sw0);
            ldsm4t(a[kk][1], ra + ko + sw1);
        }
#pragma unroll
        for (int kk = 0; kk < 4; kk++) {
            mma16816(acc[kk & 1][0], a[kk][0], b[j][kk][0], b[j][kk][1]);
            mma16816(acc[kk & 1][1], a[kk][1], b[j][kk][0], b[j][kk][1]);
        }
        __syncwarp();
        if (lane == 0) mbar_arrive(sbase + OFF_BAR + 8 * NSTAGE + 8 * s);
    }
    Acc r;
#pragma unroll
    for (int mt = 0; mt < 2; mt++)
#pragma unroll
        for (int k = 0; k < 4; k++) r.v[mt][k] = acc[0][mt][k] + acc[1][mt][k];
    return r;
}
template <int BAR>
__device__ __forceinline__ float reduce4(const Acc& a, uint32_t redaddr) {
    const int tid = threadIdx.x - 32 * PROD_FIRST, w = (tid >> 5) & 3, lane = tid & 31;
    const int g = lane >> 2, t = lane & 3;
    if (t < 2) {
        const uint32_t ra = redaddr + ((w * 4 + 2 * t) * 40 + g) * 4;
#pragma unroll
        for (int mt = 0; mt < 2; mt++) {
            sts32(ra + mt * 64, __float_as_uint(a.v[mt][0]));
            sts32(ra + mt * 64 + 160, __float_as_uint(a.v[mt][1]));
            sts32(ra + mt * 64 + 32, __float_as_uint(a.v[mt][2]));
            sts32(ra + mt * 64 + 192, __float_as_uint(a.v[mt][3]));
        }
    }
    asm volatile("bar.sync %0, 128;" ::"n"(BAR) : "memory");
    const uint32_t rb = redaddr + (w * 40 + lane) * 4;
    return (__uint_as_float(lds32(rb)) + __uint_as_float(lds32(rb + 640))) +
           (__uint_as_float(lds32(rb + 1280)) + __uint_as_float(lds32(rb + 1920)));
}

__device__ __noinline__ void gather8(const unsigned long long* src, int s1, uint32_t dst, int d1, uint32_t pend, uint32_t tag,
                                     uint32_t slp) {
    uint32_t spins = 0;
    while (true) {
        unsigned long long a[8], b[8];
#pragma unroll
        for (int k = 0; k < 8; k++)
            if (pend & (1u << k)) ld_pkt2(src + (k >> 1) * s1 + (k & 1) * 256, a[k], b[k]);
#pragma unroll
        for (int k = 0; k < 8; k++) {
            if ((pend & (1u << k)) && (uint32_t)(a[k] >> 32) == tag && (uint32_t)(b[k] >> 32) == tag) {
                sts64(dst + (k >> 1) * d1 + (k & 1) * 1024, (uint32_t)a[k], (uint32_t)b[k]);
                pend &= ~(1u << k);
            }
        }
        if (!pend) break;
        if (++spins > SPIN_LIMIT) __trap();
        __nanosleep(slp);
    }
}

__device__ __forceinline__ void gather_o(const unsigned long long* srcA, const unsigned long long* srcB, uint32_t dst,
                                         uint32_t pend, uint32_t tag, uint32_t slp) {
    constexpr int NCH = NPAIR + (KROWS + 511) / 512;
    uint32_t spins = 0;
    while (true) {
        unsigned long long a[4][NCH], b[4][NCH];
#pragma unroll
        for (int k = 0; k < 4; k++)
#pragma unroll
            for (int j = 0; j < NCH; j++)
                if (pend & (1u << (k * 4 + j)))
                    ld_pkt2((j < NPAIR ? srcA + j * 256 : srcB + (j - NPAIR) * 256) + k * 2048, a[k][j], b[k][j]);
#pragma unroll
        for (int k = 0; k < 4; k++)
#pragma unroll
            for (int j = 0; j < NCH; j++)
                if ((pend & (1u << (k * 4 + j))) && (uint32_t)(a[k][j] >> 32) == tag && (uint32_t)(b[k][j] >> 32) == tag) {
                    sts64(dst + k * (VPO * 2) + j * 1024, (uint32_t)a[k][j], (uint32_t)b[k][j]);
                    pend &= ~(1u << (k * 4 + j));
                }
        if (!pend) break;
        if (++spins > SPIN_LIMIT) __trap();
        __nanosleep(slp);
    }
}

template <int N, class F>
__device__ __forceinline__ void gather_issue(unsigned long long (&a)[N], unsigned long long (&b)[N], F addr) {
#pragma unroll
    for (int k = 0; k < N; k++) ld_pkt2(addr(k), a[k], b[k]);
}
template <int N, class F>
__device__ __forceinline__ void gather_finish(unsigned long long (&a)[N], unsigned long long (&b)[N], F addr, uint32_t tag,
                                              uint32_t slp) {
    uint32_t spins = 0;
    while (true) {
        uint32_t pend = 0;
#pragma unroll
        for (int k = 0; k < N; k++)
            if ((uint32_t)(a[k] >> 32) != tag || (uint32_t)(b[k] >> 32) != tag) pend |= 1u << k;
        if (!pend) break;
        if (++spins > SPIN_LIMIT) __trap();
        __nanosleep(slp);
#pragma unroll
        for (int k = 0; k < N; k++)
            if (pend & (1u << k)) ld_pkt2(addr(k), a[k], b[k]);
    }
    __syncwarp();
}
template <int BAR>
__device__ __forceinline__ float reduce8(const float (&v)[2][4], uint32_t redaddr, int wl, int lane) {
    const int g = lane >> 2, t = lane & 3;
    const uint32_t ra = redaddr + ((wl * 2 + (t >> 1)) * 168 + (t & 1) * 80 + g) * 4;
#pragma unroll
    for (int mt = 0; mt < 2; mt++) {
        sts32(ra + mt * 64, __float_as_uint(v[mt][0]));
        sts32(ra + mt * 64 + 160, __float_as_uint(v[mt][1]));
        sts32(ra + mt * 64 + 32, __float_as_uint(v[mt][2]));
        sts32(ra + mt * 64 + 192, __float_as_uint(v[mt][3]));
    }
    asm volatile("bar.sync %0, 128;" ::"n"(BAR) : "memory");
    const uint32_t rb = redaddr + (wl * 40 + lane) * 4;
    float e[8];
#pragma unroll
    for (int k = 0; k < 8; k++) e[k] = __uint_as_float(lds32(rb + k * 672));
    return ((e[0] + e[1]) + (e[2] + e[3])) + ((e[4] + e[5]) + (e[6] + e[7]));
}

__global__ void __cluster_dims__(2, 1, 1)
__launch_bounds__(NTHREADS, 1)
fused_decode_kernel(const __nv_bfloat16* __restrict__ x,
                    const __nv_bfloat16* __restrict__ gate_w, const __nv_bfloat16* __restrict__ b1,
                    const __nv_bfloat16* __restrict__ b2, __nv_bfloat16* __restrict__ out,
                    const __grid_constant__ CUtensorMap tm_wq, const __grid_constant__ CUtensorMap tm_w1,
                    const __grid_constant__ CUtensorMap tm_k, const __grid_constant__ CUtensorMap tm_v,
                    const __grid_constant__ CUtensorMap tm_w2, const __grid_constant__ CUtensorMap tm_wo,
                    const __grid_constant__ CUtensorMap tm_wp) {
    extern __shared__ unsigned char smem_raw[];
    const uint64_t pol = policy_evict_first();
    const uint32_t raw_addr = smem_u32(smem_raw);
    const uint32_t pad = (1024 - (raw_addr & 1023)) & 1023;
    unsigned char* sm = smem_raw + pad;
    const uint32_t sbase = raw_addr + pad;

    const int tid = ltid(), w = tid >> 5, lane = tid & 31;
    const int c = blockIdx.x;
    const int hkv = c >> 5, bb = (c >> 3) & 3, sp = c & 7;
    const int fj = c & 31, fr = c >> 5;
    const bool has_w1 = c < 112;
    const int nkv0 = KV_ID;
    const uint32_t bar_full = sbase + OFF_BAR, bar_empty = sbase + OFF_BAR + 8 * NSTAGE;
    const uint32_t bar_pair = sbase + OFF_BAR + 16 * NSTAGE;

    if (tid == 256) {
#pragma unroll
        for (int s = 0; s < 4; s++) mbar_init(bar_full + 8 * s, 1);
        asm volatile("fence.mbarrier_init.release.cluster;" ::: "memory");
#pragma unroll
        for (int s = 0; s < 4; s++) {
            if (s < DEPTH) {
                mbar_expect_tx(bar_full + 8 * s, SLOT);
                tma2d(sbase + s * SLOT, &tm_wq, c * 32, s * 256, bar_full + 8 * s, pol);
            }
        }
#pragma unroll
        for (int s = 0; s < NSTAGE; s++) {
            if (s >= 4) mbar_init(bar_full + 8 * s, 1);
            mbar_init(bar_empty + 8 * s, 4);
        }
        mbar_init(bar_pair, 1);
        sts64(sbase + OFF_MISC + 32, 0u, 0u);
        asm volatile("fence.mbarrier_init.release.cluster;" ::: "memory");
        mbar_expect_tx(bar_pair, 1024);
    }
    if (w == 8) {
        __syncwarp();
        asm volatile("bar.arrive 2, %0;" ::"n"(NTHREADS) : "memory");
        asm volatile("barrier.cluster.arrive.relaxed.aligned;" ::: "memory");
        if (lane == 0) {
            const int nslots = has_w1 ? 50 : 46;
#pragma unroll 1
            for (int n = (DEPTH < 4 ? DEPTH : 4); n < nslots; n++) {
                const int s = n % NSTAGE;
                const uint32_t dst = sbase + s * SLOT;
                const uint32_t fb = bar_full + 8 * s;
                const int id = (!has_w1 && n >= W1_ID) ? n + 4 : n;
                const CUtensorMap* m;
                int c0, c1, d0 = 0, d1 = 0;
                uint32_t bytes = SLOT;
                if (id < 4) {
                    m = &tm_wq;
                    c0 = c * 32; c1 = id * 256;
                } else if (id >= W1_ID && id < W1_ID + 4) {
                    m = &tm_w1;
                    c0 = c * 32; c1 = (id - W1_ID) * 256;
                } else if (id < 42) {
                    const int j = id - KV_ID;
                    m = (j & 2) ? &tm_v : &tm_k;
                    c0 = 0; c1 = (bb * 4 + hkv) * 8192 + (sp >> 1) * 2048 + (j >> 2) * 256 + (sp & 1) * 128 + (j & 1) * 64;
                    d0 = 64;
                } else if (id < 46) {
                    m = &tm_w2;
                    c0 = fj * 32; c1 = fr * 896 + (id - 42) * 224;
                    bytes = 224 * 64;
                } else if (id < 50 - NPAIR) {
                    m = &tm_wo;
                    c0 = fj * 32; c1 = fr * KROWS + (id - 46) * 256;
                } else {
                    m = &tm_wp;
                    c0 = (c >> 1) * 16; c1 = 4 * KROWS + (c & 1) * PROWS + (id - (50 - NPAIR)) * 512;
                    d1 = 256;
                }
                int dep = (id >= TAIL2_AT) ? DEPTH_TAIL2 : (id >= TAIL_AT) ? DEPTH_TAIL : DEPTH;
                if (id < PACE_END) dep = max(dep + (int)lds32(sbase + OFF_MISC + 32), id >= PACE_SYM ? dep : 1);
                const int nb = (n >= nkv0 + 34 && n - dep < nkv0 + 34) ? n - dep - 2 : n - dep;
                const bool scr = (id == SCR_ID || id == SCR_ID + 1);
                if (nb >= 0 && !scr) mbar_wait(bar_full + 8 * (nb % NSTAGE), (nb / NSTAGE) & 1);
                if (n >= NSTAGE) mbar_wait(bar_empty + 8 * s, ((n / NSTAGE) - 1) & 1);
                if (n == nkv0 + 32 + NSTAGE) mbar_wait(bar_empty + 8 * (s + 1), ((n / NSTAGE) - 1) & 1);
                if (scr) {
                    mbar_arrive(fb);
                } else {
                    mbar_expect_tx(fb, bytes);
                    tma2d(dst, m, c0, c1, fb, pol);
                    if (d0 | d1) tma2d(dst + 8192, m, c0 + d0, c1 + d1, fb, pol);
                }
                sts32(sbase + OFF_MISC + 36, (uint32_t)(n + 1));
            }
            sts32(sbase + OFF_MISC + 36, 64u);
        }
        return;
    }

    if (w == 9) {
        asm volatile("barrier.cluster.arrive.relaxed.aligned;" ::: "memory");
        asm volatile("bar.sync 2, %0;" ::"n"(NTHREADS) : "memory");
        if (lane == 0) {
            const uint32_t base = (lds32(sbase + OFF_MISC + 16) - 1u) * (uint32_t)(NCTA * PACE_END);
            int last = 0, nl = 0;
#pragma unroll 1
            for (uint32_t spins = 0; spins < (1u << 16); spins++) {
                const int iss = (int)lds32(sbase + OFF_MISC + 36);
                nl = max(nl, iss - 8);
                while (nl < iss && mbar_test(bar_full + 8 * (nl % NSTAGE), (nl / NSTAGE) & 1)) nl++;
                const int p = (!has_w1 && nl > W1_ID) ? nl + 4 : nl;
                if (p >= PACE_END - 1) break;
                if (p <= last) { __nanosleep(PACE_SLEEP); continue; }
                uint32_t old;
                asm volatile("atom.relaxed.gpu.global.add.u32 %0, [%1], %2;" : "=r"(old) : "l"(&g_prog), "r"(p - last) : "memory");
                last = p;
                const int lead = p * NCTA - (int)(old - base) - PACE_OFF;
                int adj = 0;
                if (lead < -PACE_G) adj = 1;
                if (lead > PACE_G) adj = -1;
                if (PACE_MAX > 1) {
                    if (lead < -3 * PACE_G) adj = 2;
                    if (lead > 3 * PACE_G) adj = -2;
                }
                if (p < PACE_START) adj = max(adj, 0);
                if (p >= PACE_SYM - 2) adj = lead < -PACE_T2 ? 2 : lead < -PACE_T1 ? 1 : 0;
                sts32(sbase + OFF_MISC + 32, (uint32_t)adj);
            }
            asm volatile("red.relaxed.gpu.global.add.u32 [%0], %1;" ::"l"(&g_prog), "r"(PACE_END - last) : "memory");
        }
        return;
    }
    asm volatile("barrier.cluster.arrive.relaxed.aligned;" ::: "memory");
    float2* ml = reinterpret_cast<float2*>(sm + OFF_ML);
    float* s_gate = reinterpret_cast<float*>(sm + OFF_MISC);
    uint32_t* s_tag = reinterpret_cast<uint32_t*>(sm + OFF_MISC + 16);
    const int g = lane >> 2, t = lane & 3;
    const int gsel = w >> 2, wl = w & 3;

    float b1v = 0.f, b2v;
    {
        const int row = wl;
        uint4 v[4], gw[4];
#pragma unroll
        for (int i = 0; i < 4; i++) {
            v[i] = *reinterpret_cast<const uint4*>(x + row * 1024 + (i * 32 + lane) * 8);
            gw[i] = *reinterpret_cast<const uint4*>(gate_w + (i * 32 + lane) * 8);
        }
        if (has_w1) b1v = __bfloat162float(b1[c * 32 + lane]);
        b2v = __bfloat162float(b2[(c >> 1) * 16 + (lane & 15)]);
        if (tid == 0) {
            unsigned e;
            asm volatile("ld.relaxed.gpu.global.u32 %0, [%1];" : "=r"(e) : "l"(&g_epoch) : "memory");
            *s_tag = e + 1;
        }
        const uint32_t* vv = reinterpret_cast<const uint32_t*>(v);
        const uint32_t* gg = reinterpret_cast<const uint32_t*>(gw);
        float s = 0.f;
        if (gsel == 0) {
#pragma unroll
            for (int i = 0; i < 16; i++) s += bf_lo(vv[i]) + bf_hi(vv[i]);
        } else {
#pragma unroll
            for (int i = 0; i < 16; i++) s += bf_lo(vv[i]) * bf_lo(gg[i]) + bf_hi(vv[i]) * bf_hi(gg[i]);
        }
#pragma unroll
        for (int o = 16; o > 0; o >>= 1) s += __shfl_xor_sync(0xffffffffu, s, o);
        if (gsel == 0) {
            const float mean = s * (1.0f / 1024.0f);
            float q = 0.f;
#pragma unroll
            for (int i = 0; i < 16; i++) {
                const float d0 = bf_lo(vv[i]) - mean, d1 = bf_hi(vv[i]) - mean;
                q += d0 * d0 + d1 * d1;
            }
#pragma unroll
            for (int o = 16; o > 0; o >>= 1) q += __shfl_xor_sync(0xffffffffu, q, o);
            const float rstd = 1.0f / sqrtf(q * (1.0f / 1024.0f) + 1e-5f);
#pragma unroll
            for (int i = 0; i < 4; i++) {
                uint4 y;
                y.x = pack_bf16((bf_lo(v[i].x) - mean) * rstd, (bf_hi(v[i].x) - mean) * rstd);
                y.y = pack_bf16((bf_lo(v[i].y) - mean) * rstd, (bf_hi(v[i].y) - mean) * rstd);
                y.z = pack_bf16((bf_lo(v[i].z) - mean) * rstd, (bf_hi(v[i].z) - mean) * rstd);
                y.w = pack_bf16((bf_lo(v[i].w) - mean) * rstd, (bf_hi(v[i].w) - mean) * rstd);
                *reinterpret_cast<uint4*>(sm + OFF_VB + (row * VP + (i * 32 + lane) * 8) * 2) = y;
            }
        } else {
#pragma unroll
            for (int i = 0; i < 4; i++)
                *reinterpret_cast<uint4*>(sm + OFF_VA + (row * VP + (i * 32 + lane) * 8) * 2) = v[i];
            if (lane == 0) s_gate[row] = 1.0f / (1.0f + __expf(-s));
        }
    }
    asm volatile("bar.sync 2, %0;" ::"n"(NTHREADS) : "memory");
    const uint32_t tag = *s_tag;

    const uint32_t t3 = tag & 7u;
    const int lt = tid & 127;
    uint32_t* const fxp = &g_fx[(fj * 4 + (lane >> 4) * 2 + (wl >> 1)) * 256 + gsel * 128 + fr * 32 + (wl & 1) * 16 + (lane & 15)];
    auto pub_fx = [&](float v) {
        red_x32(fxp, tagf(v, 4u));
    };
    const int hpos = ((lane >> 1) & 8) | (lane & 6) | ((lane >> 3) & 1);
    auto prewrite = [&]() {
        const uint32_t iv = t3 ^ 4u;
        const int dest = (c & ~7) + w;
        st_u4(&g_px[dest * 1024 + sp * 128 + lane * 4], iv, iv, iv, iv);
        if (lane < 2) st_u4(&g_ml[dest * 64 + sp * 8 + lane * 4], iv, iv, 0u, 0u);
        if (NPAIR < 4 || gsel == 0) st_u32(fxp, iv);
        if (gsel == 0) {
            if (!(lane & 1) && has_w1) st_pkt(&g_hx[w * 1792 + c * 16 + hpos], 0ull);
        } else if (g < 2) {
            st_pkt2(&g_ox[bb * 2048 + (hkv * 8 + sp) * 64 + wl * 16 + g * 8 + t * 2], 0ull, 0ull);
        }
    };
    if (gsel == 0) {
        const float s = reduce4<3>(gemv4(sbase, 0, 16, sbase + OFF_VA), sbase + OFF_RED);
        const float nb = __shfl_down_sync(0xffffffffu, s, 1);
        if (!(lane & 1)) st_pkt(&g_qx[w * 2048 + c * 16 + (lane >> 1)], mkpkt(pack_bf16(s, nb), tag));
    } else {
        mbar_wait(bar_full + 8 * QWAIT, 0);
        gather8(&g_qx[bb * 2048 + hkv * 512 + 2 * lt], 256, sbase + OFF_QS + (lt >> 5) * QS_PITCH * 2 + (lt & 31) * 8,
                4 * QS_PITCH * 2, 0x5u, tag, QSLEEP);
    }
    cons_sync();
    const float sc = 0.08838834764831845f * 1.4426950408889634f;
    {
        uint32_t qf[8][2];
#pragma unroll
        for (int ks = 0; ks < 8; ks++) {
            const uint32_t qa = sbase + OFF_QS + (g * QS_PITCH + ks * 16 + 2 * t) * 2;
            qf[ks][0] = lds32(qa);
            qf[ks][1] = lds32(qa + 16);
        }
        float o[8][4];
#pragma unroll
        for (int i = 0; i < 8; i++) { o[i][0] = o[i][1] = o[i][2] = o[i][3] = 0.f; }
        float m0 = -INFINITY, m1 = -INFINITY, l0 = 0.f, l1 = 0.f;
        {
            const int krow = wl * 16 + (lane & 7) + ((lane >> 3) & 1) * 8;
            const uint32_t koff = krow * 128;
            const int kx = krow & 7, kc = lane >> 4;
            const int vrow = wl * 16 + (lane & 7) + (lane >> 4) * 8;
            const uint32_t voff = vrow * 128;
            const int vx = vrow & 7, vc = (lane >> 3) & 1;
#pragma unroll 1
            for (int it = 0; it < 8; it++) {
                const int nk = nkv0 + it * 4 + gsel, sk = nk % NSTAGE;
                const int nv = nk + 2, sv = nv % NSTAGE;
                const uint32_t kb = sbase + sk * SLOT, vb = sbase + sv * SLOT;
                if (it == PW_IT) prewrite();
                mbar_wait(bar_full + 8 * sk, (nk / NSTAGE) & 1);
                float s0[4] = {0.f, 0.f, 0.f, 0.f}, s1[4] = {0.f, 0.f, 0.f, 0.f};
#pragma unroll
                for (int k4 = 0; k4 < 4; k4++) {
                    uint32_t a[4], a2[4];
                    const uint32_t sw = ((k4 * 2 + kc) ^ kx) << 4;
                    ldsm4(a, kb + koff + sw);
                    ldsm4(a2, kb + 8192 + koff + sw);
                    mma16816(s0, a, qf[k4][0], qf[k4][1]);
                    mma16816(s1, a2, qf[4 + k4][0], qf[4 + k4][1]);
                }
                __syncwarp();
                if (lane == 0) mbar_arrive(bar_empty + 8 * sk);
                const float c0 = s0[0] + s1[0], c1 = s0[1] + s1[1], c2 = s0[2] + s1[2], c3 = s0[3] + s1[3];
                float mx0 = fmaxf(c0, c2), mx1 = fmaxf(c1, c3);
#pragma unroll
                for (int off = 4; off < 32; off <<= 1) {
                    mx0 = fmaxf(mx0, __shfl_xor_sync(0xffffffffu, mx0, off));
                    mx1 = fmaxf(mx1, __shfl_xor_sync(0xffffffffu, mx1, off));
                }
                const float mn0 = fmaxf(m0, mx0), mn1 = fmaxf(m1, mx1);
                const float f0 = exp2f((m0 - mn0) * sc), f1 = exp2f((m1 - mn1) * sc);
                m0 = mn0; m1 = mn1;
                const float ms0 = mn0 * sc, ms1 = mn1 * sc;
                const float p0 = exp2f(fmaf(c0, sc, -ms0)), p1 = exp2f(fmaf(c1, sc, -ms1));
                const float p2 = exp2f(fmaf(c2, sc, -ms0)), p3 = exp2f(fmaf(c3, sc, -ms1));
                l0 = l0 * f0 + p0 + p2;
                l1 = l1 * f1 + p1 + p3;
                const uint32_t pb0 = movtrans(pack_bf16(p0, p1));
                const uint32_t pb1 = movtrans(pack_bf16(p2, p3));
#pragma unroll
                for (int i = 0; i < 8; i++) { o[i][0] *= f0; o[i][1] *= f1; o[i][2] *= f0; o[i][3] *= f1; }
                mbar_wait(bar_full + 8 * sv, (nv / NSTAGE) & 1);
#pragma unroll
                for (int mt = 0; mt < 8; mt++) {
                    uint32_t a[4];
                    ldsm4t(a, vb + (mt >> 2) * 8192 + voff + ((((mt & 3) * 2 + vc) ^ vx) << 4));
                    mma16816(o[mt], a, pb0, pb1);
                }
                __syncwarp();
                if (lane == 0) mbar_arrive(bar_empty + 8 * sv);
            }
        }
        {
            const int ns = nkv0 + 32;
            const int ss = ns % NSTAGE;
            float* scr = reinterpret_cast<float*>(sm + ss * SLOT);
#pragma unroll
            for (int off = 4; off < 32; off <<= 1) {
                l0 += __shfl_xor_sync(0xffffffffu, l0, off);
                l1 += __shfl_xor_sync(0xffffffffu, l1, off);
            }
            {
                mbar_wait(bar_full + 8 * (ss + gsel), (ns / NSTAGE) & 1);
                if (g == 0) {
                    ml[w * 8 + 2 * t] = make_float2(m0, l0);
                    ml[w * 8 + 2 * t + 1] = make_float2(m1, l1);
                }
                float* sw = scr + w * 1024;
#pragma unroll
                for (int mt = 0; mt < 8; mt++) {
                    const int d0 = (mt * 16 + g) ^ (t << 3), d1 = (mt * 16 + g + 8) ^ (t << 3);
                    sw[(2 * t) * 128 + d0] = o[mt][0];
                    sw[(2 * t + 1) * 128 + d0] = o[mt][1];
                    sw[(2 * t) * 128 + d1] = o[mt][2];
                    sw[(2 * t + 1) * 128 + d1] = o[mt][3];
                }
                asm volatile("fence.proxy.async.shared::cta;" ::: "memory");
            }
            cons_sync();
            const int head = w;
            float M = -INFINITY;
#pragma unroll
            for (int ww = 0; ww < 8; ww++) M = fmaxf(M, ml[ww * 8 + head].x);
            M = __uint_as_float(tagf(M, t3));
            float L = 0.f;
            float4 acc = make_float4(0.f, 0.f, 0.f, 0.f);
            const int d4 = (lane * 4) ^ ((head >> 1) << 3);
#pragma unroll
            for (int ww = 0; ww < 8; ww++) {
                const float2 v = ml[ww * 8 + head];
                const float f = exp2f((v.x - M) * sc);
                L += f * v.y;
                const float4 ov = *reinterpret_cast<const float4*>(scr + ww * 1024 + head * 128 + d4);
                acc.x += f * ov.x; acc.y += f * ov.y; acc.z += f * ov.z; acc.w += f * ov.w;
            }
            const int dest = (c & ~7) + head;
            {
                unsigned long long* pp = reinterpret_cast<unsigned long long*>(&g_px[dest * 1024 + sp * 128 + lane * 4]);
                red_x64(pp, mkpkt(tagf(acc.x, 4u), tagf(acc.y, 4u)));
                red_x64(pp + 1, mkpkt(tagf(acc.z, 4u), tagf(acc.w, 4u)));
                if (lane == 0)
                    red_x64(reinterpret_cast<unsigned long long*>(&g_ml[dest * 64 + sp * 8]), mkpkt(tagf(M, 4u), tagf(L, 4u)));
            }
            __syncwarp();
            if (lane == 0) mbar_arrive(bar_empty + 8 * (ss + gsel));
        }
    }
    if (gsel == 0) {
        if (has_w1) {
            float u = reduce4<3>(gemv4(sbase, W1_ID, 16, sbase + OFF_VB), sbase + OFF_RED);
            u += b1v;
            u = 0.5f * u * (1.0f + tanhf(0.7978845608028654f * (u + 0.044715f * u * u * u)));
            const float un = __shfl_down_sync(0xffffffffu, u, 1);
            if (!(lane & 1)) red_x64(&g_hx[w * 1792 + c * 16 + hpos], mkpkt(pack_bf16(u, un), tag));
        }
        const int nw2 = has_w1 ? 42 : 38;
        float fs;
        {
            const int rin = ((lane >> 4) << 3) + (lane & 7);
            const uint32_t sw0 = ((((lane >> 3) & 1) ^ ((rin >> 1) & 3)) << 4) + rin * 64, sw1 = sw0 ^ 32;
            const unsigned long long* hsrc = &g_hx[(g & 3) * 1792 + fr * 448 + (2 * wl + (g >> 2)) * 8 + 2 * t];
            auto haddr = [&](int k) { return hsrc + k * 64; };
            uint32_t a[7][4][4];
            unsigned long long ba[7], bb2[7];
#pragma unroll
            for (int i7 = 0; i7 < 7; i7++) {
                const int P = wl + 4 * i7, sl = (P * 37) >> 8, n = nw2 + sl;
                mbar_wait(bar_full + 8 * (n % NSTAGE), (n / NSTAGE) & 1);
                const uint32_t ra = sbase + (n % NSTAGE) * SLOT + (P - 7 * sl) * 2048;
                ldsm4t(a[i7][0], ra + sw0);
                ldsm4t(a[i7][1], ra + sw1);
                ldsm4t(a[i7][2], ra + 1024 + sw0);
                ldsm4t(a[i7][3], ra + 1024 + sw1);
                if (i7 == HX_AT) {
                    const int k = has_w1 ? HXWAIT : HXWAIT_L;
                    if (k >= 0) mbar_wait(bar_full + 8 * ((nkv0 + 34 + k) % NSTAGE), ((nkv0 + 34 + k) / NSTAGE) & 1);
                    gather_issue<7>(ba, bb2, haddr);
                }
            }
            gather_finish<7>(ba, bb2, haddr, tag, POLL_SLEEP);
            float acc[2][4][4] = {};
#pragma unroll
            for (int i7 = 0; i7 < 7; i7++)
#pragma unroll
                for (int q = 0; q < 4; q++) mma16816(acc[i7 & 1][q], a[i7][q], (uint32_t)ba[i7], (uint32_t)bb2[i7]);
            float v[2][4];
#pragma unroll
            for (int mt = 0; mt < 2; mt++)
#pragma unroll
                for (int k = 0; k < 4; k++)
                    v[mt][k] = t < 2 ? acc[0][mt][k] + acc[1][mt][k] : acc[0][2 + mt][k] + acc[1][2 + mt][k];
            fs = reduce8<3>(v, sbase + OFF_VB, wl, lane);
        }
        pub_fx(fs * (1.0f - s_gate[w]));
        if (w == 0) {
            {
                const int nl = nw2 + 7 - NPAIR;
                mbar_wait(bar_full + 8 * (nl % NSTAGE), (nl / NSTAGE) & 1);
            }
            uint32_t v[8] = {0u, 0u, 0u, 0u, 0u, 0u, 0u, 0u};
            uint32_t spins = 0, pend = 0xffu;
            __nanosleep(FX_SLEEP0);
            while (true) {
#pragma unroll
                for (int k = 0; k < 8; k++)
                    if (pend & (1u << k)) v[k] = ld_u32(&g_fx[c * 256 + k * 32 + lane]);
#pragma unroll
                for (int k = 0; k < 8; k++)
                    if (__all_sync(0xffffffffu, !((v[k] ^ t3) & 7u))) pend &= ~(1u << k);
                if (!pend) break;
                if (++spins > SPIN_LIMIT) __trap();
                __nanosleep(POLL_SLEEP2);
            }
            float f = fmaf(1.0f - s_gate[(c & 1) * 2 + (lane >> 4)], b2v,
                           ((__uint_as_float(v[0]) + __uint_as_float(v[1])) + (__uint_as_float(v[2]) + __uint_as_float(v[3]))) +
                               ((__uint_as_float(v[4]) + __uint_as_float(v[5])) + (__uint_as_float(v[6]) + __uint_as_float(v[7]))));
            spins = 0;
            while (!mbar_try_cluster(bar_pair, 0)) {
                if (++spins > (1u << 18)) __trap();
            }
            const uint32_t xa = sbase + OFF_XB + ((lane & 7) * 4 + ((lane >> 3) & 1) * 2 + (lane >> 4)) * 4;
            float e[8];
#pragma unroll
            for (int k = 0; k < 8; k++) e[k] = __uint_as_float(lds32(xa + k * 128));
            f += ((e[0] + e[1]) + (e[2] + e[3])) + ((e[4] + e[5]) + (e[6] + e[7]));
            out[((c & 1) * 2 + (lane >> 4)) * 1024 + (c >> 1) * 16 + (lane & 15)] = __float2bfloat16(f);
            if (c == 0 && lane == 0)
                asm volatile("st.relaxed.gpu.global.u32 [%0], %1;" ::"l"(&g_epoch), "r"(tag) : "memory");
        }
    } else {
        {
            {
                const int k = has_w1 ? PXWAIT : PXWAIT_L;
                if (k >= 0) mbar_wait(bar_full + 8 * ((nkv0 + 34 + k) % NSTAGE), ((nkv0 + 34 + k) / NSTAGE) & 1);
            }
            const uint32_t* src = &g_px[c * 1024 + g * 128 + wl * 32 + t * 4];
            uint4 pv, pw;
            unsigned long long pml;
            uint32_t spins = 0;
            while (true) {
                pv = ld_u4(src);
                pw = ld_u4(src + 16);
                pml = ld_pkt(reinterpret_cast<const unsigned long long*>(&g_ml[c * 64 + g * 8]));
                const uint32_t bad = ((pv.x ^ t3) | (pv.y ^ t3) | (pv.z ^ t3) | (pv.w ^ t3) | (pw.x ^ t3) | (pw.y ^ t3) | (pw.z ^ t3) |
                                      (pw.w ^ t3) | ((uint32_t)pml ^ t3) | ((uint32_t)(pml >> 32) ^ t3)) & 7u;
                if (!bad) break;
                if (++spins > SPIN_LIMIT) __trap();
                __nanosleep(POLL_SLEEP);
            }
            __syncwarp();
            const float pm = __uint_as_float((uint32_t)pml);
            float M = pm;
#pragma unroll
            for (int off = 4; off < 32; off <<= 1) M = fmaxf(M, __shfl_xor_sync(0xffffffffu, M, off));
            const float f = exp2f((pm - M) * sc);
            float v[9] = {f * __uint_as_float(pv.x), f * __uint_as_float(pv.y), f * __uint_as_float(pv.z), f * __uint_as_float(pv.w),
                          f * __uint_as_float(pw.x), f * __uint_as_float(pw.y), f * __uint_as_float(pw.z), f * __uint_as_float(pw.w),
                          f * __uint_as_float((uint32_t)(pml >> 32))};
#pragma unroll
            for (int off = 4; off < 32; off <<= 1)
#pragma unroll
                for (int k = 0; k < 9; k++) v[k] += __shfl_xor_sync(0xffffffffu, v[k], off);
            const float r = 1.0f / v[8];
            if (g < 2) {
                const float a0 = g ? v[4] : v[0], a1 = g ? v[5] : v[1], a2 = g ? v[6] : v[2], a3 = g ? v[7] : v[3];
                red_x64(&g_ox[bb * 2048 + (hkv * 8 + sp) * 64 + wl * 16 + g * 8 + t * 2], mkpkt(pack_bf16(a0 * r, a1 * r), tag));
                red_x64(&g_ox[bb * 2048 + (hkv * 8 + sp) * 64 + wl * 16 + g * 8 + t * 2 + 1], mkpkt(pack_bf16(a2 * r, a3 * r), tag));
            }
        }
        {
            const int k = has_w1 ? OXWAIT : OXWAIT_L;
            if (k >= 0) mbar_wait(bar_full + 8 * ((nkv0 + 34 + k) % NSTAGE), ((nkv0 + 34 + k) / NSTAGE) & 1);
        }
        {
            uint32_t m = (1u << NPAIR) - 1;
            if (2 * lt < KROWS / 2) m |= 1u << NPAIR;
            if (2 * lt + 256 < KROWS / 2) m |= 2u << NPAIR;
            gather_o(&g_ox[2 * KROWS + (c & 1) * (PROWS / 2) + 2 * lt], &g_ox[fr * (KROWS / 2) + 2 * lt], sbase + OFF_VA + lt * 8,
                     m * 0x1111u, tag, POLL_SLEEP);
        }
        asm volatile("bar.sync 5, 128;" ::: "memory");
        if (NPAIR < 4) {
            const int i = lane >> 3;
            const int r0 = wl * 16 + (i >> 1) * 8 + (lane & 7);
            const uint32_t sw0 = r0 * 64 + (((i & 1) ^ ((r0 >> 1) & 3)) << 4), sw1 = sw0 ^ 32;
            uint32_t zp = sbase + OFF_VA + PROWS * 2 + ((g & 3) * VPO + wl * 16 + 2 * t) * 2;
            const float gt = s_gate[wl];
            float acc[2][2][4] = {};
            int n = has_w1 ? 46 : 42;
#pragma unroll 1
            for (int j = 0; j < 4 - NPAIR; j++, n++, zp += 512) {
                uint32_t b[4][2];
#pragma unroll
                for (int kk = 0; kk < 4; kk++) {
                    b[kk][0] = g < 4 ? lds32(zp + kk * 128) : 0u;
                    b[kk][1] = g < 4 ? lds32(zp + kk * 128 + 16) : 0u;
                }
                const int s = n % NSTAGE;
                const uint32_t ra = sbase + s * SLOT;
                mbar_wait(bar_full + 8 * s, (n / NSTAGE) & 1);
                uint32_t a[4][2][4];
#pragma unroll
                for (int kk = 0; kk < 4; kk++) {
                    ldsm4t(a[kk][0], ra + kk * 4096 + sw0);
                    ldsm4t(a[kk][1], ra + kk * 4096 + sw1);
                }
#pragma unroll
                for (int kk = 0; kk < 4; kk++) {
                    mma16816(acc[kk & 1][0], a[kk][0], b[kk][0], b[kk][1]);
                    mma16816(acc[kk & 1][1], a[kk][1], b[kk][0], b[kk][1]);
                }
                Acc ao;
#pragma unroll
                for (int mt = 0; mt < 2; mt++)
#pragma unroll
                    for (int k = 0; k < 4; k++) ao.v[mt][k] = acc[0][mt][k] + acc[1][mt][k];
                const float fs = reduce4<5>(ao, sbase + OFF_RED + 2560);
                if (j == 3 - NPAIR) pub_fx(fs * gt);
            }
        }
        {
            const int i = lane >> 3;
            uint32_t bq[NPAIR][8][2];
            const uint32_t zp = sbase + OFF_VA + ((g & 3) * VPO + wl * 128 + 2 * t) * 2;
#pragma unroll
            for (int j = 0; j < NPAIR; j++)
#pragma unroll
                for (int kk = 0; kk < 8; kk++) {
                    bq[j][kk][0] = g < 4 ? lds32(zp + j * 1024 + kk * 32) : 0u;
                    bq[j][kk][1] = g < 4 ? lds32(zp + j * 1024 + kk * 32 + 16) : 0u;
                }
            const float ga0 = s_gate[(2 * t) & 3], ga1 = s_gate[(2 * t + 1) & 3];
            const uint32_t xo = sbase + OFF_XB + (((c & 1) * 4 + wl) * 32 + g * 4) * 4;
            uint32_t xa, ba;
            asm volatile("mapa.shared::cluster.u32 %0, %1, %2;" : "=r"(xa) : "r"(xo), "r"(t & 1));
            asm volatile("mapa.shared::cluster.u32 %0, %1, %2;" : "=r"(ba) : "r"(bar_pair), "r"(t & 1));
            asm volatile("barrier.cluster.wait.acquire.aligned;" ::: "memory");
            const int r0 = wl * 128 + (i >> 1) * 8 + (lane & 7);
            const uint32_t roff = r0 * 32 + (((i & 1) ^ ((r0 >> 2) & 1)) << 4);
            float acc[4][4] = {};
#pragma unroll
            for (int j = 0; j < NPAIR; j++) {
                const int n = (has_w1 ? 50 : 46) - NPAIR + j;
                const int s = n % NSTAGE;
                mbar_wait(bar_full + 8 * s, (n / NSTAGE) & 1);
                const uint32_t ra = sbase + s * SLOT + roff;
                uint32_t a[8][4];
#pragma unroll
                for (int kk = 0; kk < 8; kk++) ldsm4t(a[kk], ra + kk * 512);
#pragma unroll
                for (int kk = 0; kk < 8; kk++) {
                    mma16816(acc[kk & 3], a[kk], bq[j][kk][0], bq[j][kk][1]);
                }
            }
            if (t < 2) {
                const float p0 = ((acc[0][0] + acc[1][0]) + (acc[2][0] + acc[3][0])) * ga0;
                const float p1 = ((acc[0][1] + acc[1][1]) + (acc[2][1] + acc[3][1])) * ga1;
                const float p2 = ((acc[0][2] + acc[1][2]) + (acc[2][2] + acc[3][2])) * ga0;
                const float p3 = ((acc[0][3] + acc[1][3]) + (acc[2][3] + acc[3][3])) * ga1;
                asm volatile("st.async.weak.shared::cluster.mbarrier::complete_tx::bytes.v4.f32 [%0], {%1, %2, %3, %4}, [%5];"
                             ::"r"(xa), "f"(p0), "f"(p1), "f"(p2), "f"(p3), "r"(ba) : "memory");
            }
        }
    }
}

typedef CUresult (*EncodeFn)(CUtensorMap*, CUtensorMapDataType, cuuint32_t, void*, const cuuint64_t*, const cuuint64_t*,
                             const cuuint32_t*, const cuuint32_t*, CUtensorMapInterleave, CUtensorMapSwizzle,
                             CUtensorMapL2promotion, CUtensorMapFloatOOBfill);

void make_map(EncodeFn fn, CUtensorMap* m, const void* ptr, uint64_t inner, uint64_t rows, uint32_t box_inner,
              uint32_t box_rows, CUtensorMapSwizzle sw, CUtensorMapL2promotion prom) {
    cuuint64_t dims[2] = {inner, rows};
    cuuint64_t strides[1] = {inner * 2};
    cuuint32_t box[2] = {box_inner, box_rows};
    cuuint32_t estr[2] = {1, 1};
    fn(m, CU_TENSOR_MAP_DATA_TYPE_BFLOAT16, 2, const_cast<void*>(ptr), dims, strides, box, estr,
       CU_TENSOR_MAP_INTERLEAVE_NONE, sw, prom, CU_TENSOR_MAP_FLOAT_OOB_FILL_NONE);
}

}

extern "C" void kernel_launch(void* const* d_in, const int* in_sizes, int n_in, void* d_out, int out_size) {
    (void)in_sizes; (void)n_in; (void)out_size;
    static EncodeFn fn = nullptr;
    if (!fn) {
        void* p = nullptr;
        cudaDriverEntryPointQueryResult st;
        cudaGetDriverEntryPoint("cuTensorMapEncodeTiled", &p, cudaEnableDefault, &st);
        fn = (EncodeFn)p;
        cudaFuncSetAttribute(fused_decode_kernel, cudaFuncAttributeMaxDynamicSharedMemorySize, SMEM_BYTES);
    }
    const __nv_bfloat16* x  = (const __nv_bfloat16*)d_in[0];
    const void* kc = d_in[1];
    const void* vc = d_in[2];
    const void* wq = d_in[3];
    const void* wo = d_in[4];
    const void* w1 = d_in[6];
    const __nv_bfloat16* b1 = (const __nv_bfloat16*)d_in[7];
    const void* w2 = d_in[8];
    const __nv_bfloat16* b2 = (const __nv_bfloat16*)d_in[9];
    const __nv_bfloat16* gw = (const __nv_bfloat16*)d_in[10];

    CUtensorMap m_wq, m_w1, m_k, m_v, m_w2, m_wo, m_wp;
    make_map(fn, &m_wq, wq, 4096, 1024, 32, 256, CU_TENSOR_MAP_SWIZZLE_64B, (CUtensorMapL2promotion)PROM_WQ);
    make_map(fn, &m_w1, w1, 3584, 1024, 32, 256, CU_TENSOR_MAP_SWIZZLE_64B, (CUtensorMapL2promotion)PROM_W1);
    make_map(fn, &m_k, kc, 128, 131072, 64, 64, CU_TENSOR_MAP_SWIZZLE_128B, (CUtensorMapL2promotion)PROM_KV);
    make_map(fn, &m_v, vc, 128, 131072, 64, 64, CU_TENSOR_MAP_SWIZZLE_128B, (CUtensorMapL2promotion)PROM_KV);
    make_map(fn, &m_w2, w2, 1024, 3584, 32, 224, CU_TENSOR_MAP_SWIZZLE_64B, (CUtensorMapL2promotion)PROM_W2);
    make_map(fn, &m_wo, wo, 1024, 4096, 32, 256, CU_TENSOR_MAP_SWIZZLE_64B, (CUtensorMapL2promotion)PROM_WO);
    make_map(fn, &m_wp, wo, 1024, 4096, 16, 256, CU_TENSOR_MAP_SWIZZLE_32B, (CUtensorMapL2promotion)PROM_WP);

    fused_decode_kernel<<<NCTA, NTHREADS, SMEM_BYTES>>>(x, gw, b1, b2, (__nv_bfloat16*)d_out, m_wq, m_w1, m_k, m_v, m_w2, m_wo,
                                                        m_wp);
}
```
